```python
import torch

def _softmax(x, axis=-1):
    return torch.softmax(x, dim=axis)
def _gelu(x):
    return torch.nn.functional.gelu(x, approximate="tanh")
def _silu(x):
    return torch.nn.functional.silu(x)
def _sigmoid(x):
    return torch.sigmoid(x)
def _layernorm(x, axis=-1, eps=1e-5):
    m = x.mean(dim=axis, keepdim=True)
    v = x.var(dim=axis, keepdim=True, unbiased=False)
    return (x - m) / torch.sqrt(v + eps)
def _scatter_add(tgt, idx, src, axis=0):
    return tgt.clone().index_add_(axis, idx, src)
def _segment_sum(src, seg, n):
    out = torch.zeros((n,) + src.shape[1:], dtype=src.dtype)
    return out.index_add_(0, seg, src)
def _pad(x, pw):
    flat = tuple(v for pair in reversed(pw) for v in pair)
    return torch.nn.functional.pad(x, flat)

kernel_name = 'parallel_sum__grouped_kv_mqa__dense_activation_mish__prompt'

def setup_inputs():

    _w = (lambda a: (lambda t: t.to(torch.bfloat16) if t.is_floating_point() else t)(torch.as_tensor(a)))
    def _A_setup():
        B, S, D, H = 1, 2048, 512, 32
        Dh = D // H
        return {
            "x": _w((lambda *s: torch.randn(*s, dtype=torch.bfloat16) * 0.05)(B, S, D)),
            "wq": _w((lambda *s: torch.randn(*s, dtype=torch.bfloat16) * 0.05)(D, H * Dh)),
            "wk": _w((lambda *s: torch.randn(*s, dtype=torch.bfloat16) * 0.05)(D, Dh)),
            "wv": _w((lambda *s: torch.randn(*s, dtype=torch.bfloat16) * 0.05)(D, Dh)),
            "wo": _w((lambda *s: torch.randn(*s, dtype=torch.bfloat16) * 0.05)(H * Dh, D)),
        }
    _A_in = _A_setup()

    def _B_setup():
        B, S, D, F = 1, 2048, 512, 1792
        return {
            "x": _w((lambda *s: torch.randn(*s, dtype=torch.bfloat16) * 0.05)(B, S, D)),
            "w1": _w((lambda *s: torch.randn(*s, dtype=torch.bfloat16) * 0.8)(D, F) * (D ** -0.5)),
            "b1": _w((lambda *s: torch.randn(*s, dtype=torch.bfloat16) * 0.4)(F)),
            "w2": _w((lambda *s: torch.randn(*s, dtype=torch.bfloat16) * 0.2)(F, D) * (F ** -0.5)),
        }
    _B_in = _B_setup()

    return {
        "A_x": _A_in["x"],
        "A_wq": _A_in["wq"],
        "A_wk": _A_in["wk"],
        "A_wv": _A_in["wv"],
        "A_wo": _A_in["wo"],
        "B_x": _B_in["x"],
        "B_w1": _B_in["w1"],
        "B_b1": _B_in["b1"],
        "B_w2": _B_in["w2"],
    }

def reference(A_x, A_wq, A_wk, A_wv, A_wo, B_x, B_w1, B_b1, B_w2):
    def _A_ref(x, wq, wk, wv, wo):
        B, S, D = x.shape
        H = 32
        Dh = D // H
        q = (lambda x, *d: x.permute(*d))((x @ wq).reshape(B, S, H, Dh), 0, 2, 1, 3)
        k = x @ wk
        v = x @ wv
        scores = torch.einsum("bhqd,bkd->bhqk", q, k) * (Dh ** -0.5)
        p = _softmax(scores, axis=-1)
        o = torch.einsum("bhqk,bkd->bhqd", p, v)
        return (lambda x, *d: x.permute(*d))(o, 0, 2, 1, 3).reshape(B, S, H * Dh) @ wo

    def _B_ref(x, w1, b1, w2):
        h = torch.einsum("bsd,df->bsf", x, w1) + b1
        sp = torch.log1p(torch.exp(-torch.abs(h))) + torch.where(h > 0, h, torch.zeros_like(h))
        act = h * torch.tanh(sp)
        return torch.einsum("bsf,fd->bsd", act, w2)

    x = A_x
    xn = _layernorm(x, axis=-1)
    return x + _A_ref(xn, A_wq, A_wk, A_wv, A_wo) + _B_ref(xn, B_w1, B_b1, B_w2)
```

```cpp
#include <cuda_runtime.h>
#include <cuda_bf16.h>
#include <cuda_fp16.h>
#include <cuda.h>
#include <stdint.h>

namespace {

constexpr int S_ = 2048, D_ = 512, F_ = 1792;
constexpr float LOG2E = 1.4426950408889634f, LN2 = 0.6931471805599453f;

__device__ __align__(1024) uint8_t g_kv[8 * 20480];
__device__ __align__(1024) uint8_t g_H[16 * 32 * 16384];
__device__ __align__(1024) __nv_bfloat16 g_KV[2 * S_ * 16];
__device__ __align__(1024) uint4 g_O1[16 * 8 * 16 * 32];
__device__ __align__(1024) uint4 g_X[128 * 4 * 256];
__device__ uint32_t g_kmax[64];
__device__ unsigned g_cnt[128 * 32];
constexpr int CNT_KV = 0, CNT_DONE = 1, CNT_A = 2, CNT_O1 = 34, CNT_N = 50;

#define MARK(k)
#define MARKIF(c, k)
#define MARKP(k)
#define MARKH(k)
#define MARK2(c, k)

constexpr uint32_t U_ = 32768;
constexpr uint32_t OFF_WKV = 196608, OFF_STG = 212992, OFF_MISC = 229376;
constexpr uint32_t OFF_KV = 163840, KV_STAGE = 20480;
constexpr uint32_t G_STAGE = 32768;
constexpr int G_SLOTS = 6;
constexpr uint32_t OFF_XRES = 196608;
constexpr uint32_t OFF_KMAX = OFF_MISC + 496, OFF_BIAS = OFF_MISC + 512;
constexpr uint32_t SMEM_BYTES = OFF_MISC + 2048;
constexpr int B_X = 49, B_XE = 8, B_W = 10, B_WE = 19, B_WKV = 24, B_KF = 25, B_KE = 27, B_GF = 0, B_GE = 33,
              B_XR = 39, B_KM = 40, B_O1R = 41, B_AD = 42, B_O0D = 43, B_O1D = 44, B_KVD = 47, B_BI = 48;
constexpr uint64_t MASK8 = (31ull << B_WE) | (63ull << B_GE) | (3ull << B_KE) | (7ull << B_AD);
constexpr uint64_t MASK4 = (3ull << B_XE) | (1ull << B_KVD);

struct Params {
  CUtensorMap x3, x2, wq, w1, w1s, w2, wo, wo1;
  const __nv_bfloat16 *wk, *wv, *b1, *pw2, *pwo, *pwq;
  __nv_bfloat16* outp;
};

__device__ __forceinline__ void mbar_init(uint32_t b, int n) { asm volatile("mbarrier.init.shared::cta.b64 [%0], %1;" ::"r"(b), "r"(n) : "memory"); }
__device__ __forceinline__ void mbar_expect(uint32_t b, uint32_t bytes) { asm volatile("mbarrier.arrive.expect_tx.shared::cta.b64 _, [%0], %1;" ::"r"(b), "r"(bytes) : "memory"); }
__device__ __forceinline__ void mbar_arrive(uint32_t b) { asm volatile("mbarrier.arrive.shared::cta.b64 _, [%0];" ::"r"(b) : "memory"); }
__device__ __forceinline__ void mbar_wait(uint32_t b, uint32_t ph) {
  asm volatile(
      "{\n.reg .pred p;\n.reg .u32 n;\nmov.u32 n, 0;\n"
      "LAB_WAIT:\n"
      "mbarrier.try_wait.parity.shared::cta.b64 p, [%0], %1;\n"
      "@p bra LAB_DONE;\n"
      "add.u32 n, n, 1;\nsetp.lt.u32 p, n, 20000000;\n"
      "@p bra LAB_WAIT;\n"
      "trap;\n"
      "LAB_DONE:\n}\n" ::"r"(b), "r"(ph) : "memory");
}
__device__ __forceinline__ void mbar_sleep(uint32_t b, uint32_t ph) {
  asm volatile(
      "{\n.reg .pred p;\n.reg .u32 n;\nmov.u32 n, 0;\n"
      "LAB_WAIT:\n"
      "mbarrier.try_wait.parity.shared::cta.b64 p, [%0], %1, 200000;\n"
      "@p bra LAB_DONE;\n"
      "add.u32 n, n, 1;\nsetp.lt.u32 p, n, 10000;\n"
      "@p bra LAB_WAIT;\n"
      "trap;\n"
      "LAB_DONE:\n}\n" ::"r"(b), "r"(ph) : "memory");
}
template <int NS>
__device__ __forceinline__ void wait_counter(const unsigned* p, unsigned target) {
  asm volatile(
      "{\n.reg .pred p;\n.reg .u32 n, v;\nmov.u32 n, 0;\n"
      "LAB_WAIT:\n"
      "ld.acquire.gpu.global.u32 v, [%0];\n"
      "setp.ge.u32 p, v, %1;\n"
      "@p bra LAB_DONE;\n"
      "nanosleep.u32 %2;\n"
      "add.u32 n, n, 1;\nsetp.lt.u32 p, n, 4000000;\n"
      "@p bra LAB_WAIT;\n"
      "trap;\n"
      "LAB_DONE:\n}\n" ::"l"(p), "r"(target), "n"(NS) : "memory");
}
__device__ __forceinline__ void fence_async_all() { asm volatile("fence.proxy.async;" ::: "memory"); }
__device__ __forceinline__ void signal_counter(unsigned* p) {
  asm volatile("fence.acq_rel.gpu;\nred.relaxed.gpu.global.add.u32 [%0], 1;" ::"l"(p) : "memory");
}
__device__ __forceinline__ void tma2(uint32_t dst, const CUtensorMap* m, int c0, int c1, uint32_t bar) {
  asm volatile("cp.async.bulk.tensor.2d.shared::cluster.global.mbarrier::complete_tx::bytes [%0], [%1, {%3, %4}], [%2];" ::"r"(dst), "l"(m), "r"(bar), "r"(c0), "r"(c1) : "memory");
}
__device__ __forceinline__ void tma3(uint32_t dst, const CUtensorMap* m, int c0, int c1, int c2, uint32_t bar) {
  asm volatile("cp.async.bulk.tensor.3d.shared::cluster.global.mbarrier::complete_tx::bytes [%0], [%1, {%3, %4, %5}], [%2];" ::"r"(dst), "l"(m), "r"(bar), "r"(c0), "r"(c1), "r"(c2) : "memory");
}
__device__ __forceinline__ void tma5(uint32_t dst, const CUtensorMap* m, int c2, int c3, int c4, uint32_t bar) {
  asm volatile("cp.async.bulk.tensor.5d.shared::cluster.global.mbarrier::complete_tx::bytes [%0], [%1, {0, 0, %3, %4, %5}], [%2];" ::"r"(dst), "l"(m), "r"(bar), "r"(c2), "r"(c3), "r"(c4) : "memory");
}
__device__ __forceinline__ void tma5p(uint32_t dst, const CUtensorMap* m, int c0, int c4, uint32_t bar) {
  asm volatile("cp.async.bulk.tensor.5d.shared::cluster.global.mbarrier::complete_tx::bytes [%0], [%1, {%3, 0, 0, 0, %4}], [%2];" ::"r"(dst), "l"(m), "r"(bar), "r"(c0), "r"(c4) : "memory");
}
__device__ __forceinline__ void bulk_load(uint32_t dst, const void* src, uint32_t bytes, uint32_t bar) {
  asm volatile("cp.async.bulk.shared::cluster.global.mbarrier::complete_tx::bytes [%0], [%1], %2, [%3];" ::"r"(dst), "l"(src), "r"(bytes), "r"(bar) : "memory");
}
__device__ __forceinline__ void l2_prefetch(const void* src, uint32_t bytes) { asm volatile("cp.async.bulk.prefetch.L2.global [%0], %1;" ::"l"(src), "r"(bytes) : "memory"); }
__device__ __forceinline__ void fence_async_smem() { asm volatile("fence.proxy.async.shared::cta;" ::: "memory"); }
__device__ __forceinline__ void ldsm4(uint32_t* r, uint32_t a) { asm volatile("ldmatrix.sync.aligned.m8n8.x4.shared.b16 {%0,%1,%2,%3}, [%4];" : "=r"(r[0]), "=r"(r[1]), "=r"(r[2]), "=r"(r[3]) : "r"(a) : "memory"); }
__device__ __forceinline__ void stsm4(uint32_t a, uint32_t r0, uint32_t r1, uint32_t r2, uint32_t r3) { asm volatile("stmatrix.sync.aligned.m8n8.x4.shared.b16 [%0], {%1,%2,%3,%4};" ::"r"(a), "r"(r0), "r"(r1), "r"(r2), "r"(r3) : "memory"); }
__device__ __forceinline__ void mma_bf16(float* c, const uint32_t* a, uint32_t b0, uint32_t b1) {
  asm volatile("mma.sync.aligned.m16n8k16.row.col.f32.bf16.bf16.f32 {%0,%1,%2,%3}, {%4,%5,%6,%7}, {%8,%9}, {%0,%1,%2,%3};"
               : "+f"(c[0]), "+f"(c[1]), "+f"(c[2]), "+f"(c[3]) : "r"(a[0]), "r"(a[1]), "r"(a[2]), "r"(a[3]), "r"(b0), "r"(b1));
}
__device__ __forceinline__ uint32_t pack_bf16(float lo, float hi) { uint32_t r; asm("cvt.rn.bf16x2.f32 %0, %1, %2;" : "=r"(r) : "f"(hi), "f"(lo)); return r; }
__device__ __forceinline__ uint32_t pack_f16(float lo, float hi) { uint32_t r; asm("cvt.rn.f16x2.f32 %0, %1, %2;" : "=r"(r) : "f"(hi), "f"(lo)); return r; }
__device__ __forceinline__ float ex2(float x) { float r; asm("ex2.approx.ftz.f32 %0, %1;" : "=f"(r) : "f"(x)); return r; }
__device__ __forceinline__ float rcp(float x) { float r; asm("rcp.approx.ftz.f32 %0, %1;" : "=f"(r) : "f"(x)); return r; }
__device__ __forceinline__ void wg_fence() { asm volatile("wgmma.fence.sync.aligned;" ::: "memory"); }
__device__ __forceinline__ void wg_commit() { asm volatile("wgmma.commit_group.sync.aligned;" ::: "memory"); }
template <int N> __device__ __forceinline__ void wg_wait() { asm volatile("wgmma.wait_group.sync.aligned %0;" ::"n"(N) : "memory"); }
template <int N> __device__ __forceinline__ void pin(float* r) {
#pragma unroll
  for (int i = 0; i < N; i++) asm volatile("" : "+f"(r[i])::"memory");
}
template <int N> __device__ __forceinline__ void pin(uint32_t* r) {
#pragma unroll
  for (int i = 0; i < N; i++) asm volatile("" : "+r"(r[i])::"memory");
}
__device__ __forceinline__ uint64_t mkdesc(uint32_t addr, uint32_t lbo, uint32_t sbo, int sw) {
  return (uint64_t)((addr & 0x3FFFF) >> 4) | ((uint64_t)(lbo >> 4) << 16) | ((uint64_t)(sbo >> 4) << 32) | ((uint64_t)sw << 62);
}

__device__ __forceinline__ void wg_rs64t(float* d, const uint32_t* a, uint64_t db, int sd) {
  asm volatile("{\n.reg .pred p;\nsetp.ne.b32 p, %37, 0;\n"
    "wgmma.mma_async.sync.aligned.m64n64k16.f32.bf16.bf16 "
    "{%0, %1, %2, %3, %4, %5, %6, %7, %8, %9, %10, %11, %12, %13, %14, %15, "
    "%16, %17, %18, %19, %20, %21, %22, %23, %24, %25, %26, %27, %28, %29, %30, %31}, "
    "{%32, %33, %34, %35}, %36, p, 1, 1, 1;\n}\n"
    : "+f"(d[0]), "+f"(d[1]), "+f"(d[2]), "+f"(d[3]), "+f"(d[4]), "+f"(d[5]), "+f"(d[6]), "+f"(d[7]),
      "+f"(d[8]), "+f"(d[9]), "+f"(d[10]), "+f"(d[11]), "+f"(d[12]), "+f"(d[13]), "+f"(d[14]), "+f"(d[15]),
      "+f"(d[16]), "+f"(d[17]), "+f"(d[18]), "+f"(d[19]), "+f"(d[20]), "+f"(d[21]), "+f"(d[22]), "+f"(d[23]),
      "+f"(d[24]), "+f"(d[25]), "+f"(d[26]), "+f"(d[27]), "+f"(d[28]), "+f"(d[29]), "+f"(d[30]), "+f"(d[31])
    : "r"(a[0]), "r"(a[1]), "r"(a[2]), "r"(a[3]), "l"(db), "r"(sd));
}
__device__ __forceinline__ void wg_rs32t(float* d, const uint32_t* a, uint64_t db, int sd) {
  asm volatile("{\n.reg .pred p;\nsetp.ne.b32 p, %21, 0;\n"
    "wgmma.mma_async.sync.aligned.m64n32k16.f32.bf16.bf16 "
    "{%0, %1, %2, %3, %4, %5, %6, %7, %8, %9, %10, %11, %12, %13, %14, %15}, "
    "{%16, %17, %18, %19}, %20, p, 1, 1, 1;\n}\n"
    : "+f"(d[0]), "+f"(d[1]), "+f"(d[2]), "+f"(d[3]), "+f"(d[4]), "+f"(d[5]), "+f"(d[6]), "+f"(d[7]),
      "+f"(d[8]), "+f"(d[9]), "+f"(d[10]), "+f"(d[11]), "+f"(d[12]), "+f"(d[13]), "+f"(d[14]), "+f"(d[15])
    : "r"(a[0]), "r"(a[1]), "r"(a[2]), "r"(a[3]), "l"(db), "r"(sd));
}
__device__ __forceinline__ void wg_rs16t(float* d, const uint32_t* a, uint64_t db, int sd) {
  asm volatile("{\n.reg .pred p;\nsetp.ne.b32 p, %13, 0;\n"
    "wgmma.mma_async.sync.aligned.m64n16k16.f32.bf16.bf16 "
    "{%0, %1, %2, %3, %4, %5, %6, %7}, "
    "{%8, %9, %10, %11}, %12, p, 1, 1, 1;\n}\n"
    : "+f"(d[0]), "+f"(d[1]), "+f"(d[2]), "+f"(d[3]), "+f"(d[4]), "+f"(d[5]), "+f"(d[6]), "+f"(d[7])
    : "r"(a[0]), "r"(a[1]), "r"(a[2]), "r"(a[3]), "l"(db), "r"(sd));
}
__device__ __forceinline__ void wg_pv24(uint32_t* d, const uint32_t* a, uint64_t db, int sd) {
  asm volatile("{\n.reg .pred p;\nsetp.ne.b32 p, %11, 0;\n"
    "wgmma.mma_async.sync.aligned.m64n24k16.f16.f16.f16 "
    "{%0, %1, %2, %3, %4, %5}, "
    "{%6, %7, %8, %9}, %10, p, 1, 1, 1;\n}\n"
    : "+r"(d[0]), "+r"(d[1]), "+r"(d[2]), "+r"(d[3]), "+r"(d[4]), "+r"(d[5])
    : "r"(a[0]), "r"(a[1]), "r"(a[2]), "r"(a[3]), "l"(db), "r"(sd));
}
__device__ __forceinline__ void wg_qk64(float* d, const uint32_t* a, uint64_t db, int sd) {
  asm volatile("{\n.reg .pred p;\nsetp.ne.b32 p, %37, 0;\n"
    "wgmma.mma_async.sync.aligned.m64n64k16.f32.bf16.bf16 "
    "{%0, %1, %2, %3, %4, %5, %6, %7, %8, %9, %10, %11, %12, %13, %14, %15, "
    "%16, %17, %18, %19, %20, %21, %22, %23, %24, %25, %26, %27, %28, %29, %30, %31}, "
    "{%32, %33, %34, %35}, %36, p, 1, 1, 0;\n}\n"
    : "+f"(d[0]), "+f"(d[1]), "+f"(d[2]), "+f"(d[3]), "+f"(d[4]), "+f"(d[5]), "+f"(d[6]), "+f"(d[7]),
      "+f"(d[8]), "+f"(d[9]), "+f"(d[10]), "+f"(d[11]), "+f"(d[12]), "+f"(d[13]), "+f"(d[14]), "+f"(d[15]),
      "+f"(d[16]), "+f"(d[17]), "+f"(d[18]), "+f"(d[19]), "+f"(d[20]), "+f"(d[21]), "+f"(d[22]), "+f"(d[23]),
      "+f"(d[24]), "+f"(d[25]), "+f"(d[26]), "+f"(d[27]), "+f"(d[28]), "+f"(d[29]), "+f"(d[30]), "+f"(d[31])
    : "r"(a[0]), "r"(a[1]), "r"(a[2]), "r"(a[3]), "l"(db), "r"(sd));
}
__device__ __forceinline__ void wg_ss128t(float* d, uint64_t da, uint64_t db, int sd) {
  asm volatile("{\n.reg .pred p;\nsetp.ne.b32 p, %66, 0;\n"
    "wgmma.mma_async.sync.aligned.m64n128k16.f32.bf16.bf16 "
    "{%0, %1, %2, %3, %4, %5, %6, %7, %8, %9, %10, %11, %12, %13, %14, %15, "
    "%16, %17, %18, %19, %20, %21, %22, %23, %24, %25, %26, %27, %28, %29, %30, %31, "
    "%32, %33, %34, %35, %36, %37, %38, %39, %40, %41, %42, %43, %44, %45, %46, %47, "
    "%48, %49, %50, %51, %52, %53, %54, %55, %56, %57, %58, %59, %60, %61, %62, %63}, "
    "%64, %65, p, 1, 1, 0, 1;\n}\n"
    : "+f"(d[0]), "+f"(d[1]), "+f"(d[2]), "+f"(d[3]), "+f"(d[4]), "+f"(d[5]), "+f"(d[6]), "+f"(d[7]),
      "+f"(d[8]), "+f"(d[9]), "+f"(d[10]), "+f"(d[11]), "+f"(d[12]), "+f"(d[13]), "+f"(d[14]), "+f"(d[15]),
      "+f"(d[16]), "+f"(d[17]), "+f"(d[18]), "+f"(d[19]), "+f"(d[20]), "+f"(d[21]), "+f"(d[22]), "+f"(d[23]),
      "+f"(d[24]), "+f"(d[25]), "+f"(d[26]), "+f"(d[27]), "+f"(d[28]), "+f"(d[29]), "+f"(d[30]), "+f"(d[31]),
      "+f"(d[32]), "+f"(d[33]), "+f"(d[34]), "+f"(d[35]), "+f"(d[36]), "+f"(d[37]), "+f"(d[38]), "+f"(d[39]),
      "+f"(d[40]), "+f"(d[41]), "+f"(d[42]), "+f"(d[43]), "+f"(d[44]), "+f"(d[45]), "+f"(d[46]), "+f"(d[47]),
      "+f"(d[48]), "+f"(d[49]), "+f"(d[50]), "+f"(d[51]), "+f"(d[52]), "+f"(d[53]), "+f"(d[54]), "+f"(d[55]),
      "+f"(d[56]), "+f"(d[57]), "+f"(d[58]), "+f"(d[59]), "+f"(d[60]), "+f"(d[61]), "+f"(d[62]), "+f"(d[63])
    : "l"(da), "l"(db), "r"(sd));
}

__host__ __device__ constexpr bool is_mufu(int i) { return (0x3030 >> i) & 1; }
constexpr float P_SHIFT = 5.f;
constexpr uint32_t POLY_INIT = 9640;
constexpr float DRIFT = 0.000366f;
__device__ __forceinline__ uint32_t exp_pack(float a, float b) {
  uint32_t y;
  asm("cvt.pack.sat.s16.s32 %0, %1, %2;" : "=r"(y) : "r"(__float_as_uint(b)), "r"(__float_as_uint(a)));
  return y;
}
__device__ __forceinline__ void exp_poly(uint32_t& y, uint32_t& cm) {
  asm("lop3.b32 %0, %1, 0x03FF03FF, %0, 0xE2;" : "+r"(cm) : "r"(y));
  asm("fma.rn.f16x2 %0, %0, %1, %2;" : "+r"(y) : "r"(cm), "r"(y & 0xFC00FC00u));
}
__device__ __forceinline__ void exp_poly(uint32_t& y, uint32_t& cm, uint32_t& e, float s) {
  asm("{.reg .pred p;\nlop3.or.b32 %0|p, %2, 0x03FF03FF, %0, 0xE2, 0;\n@p ex2.approx.ftz.f32 %1, %3;}" : "+r"(cm), "+r"(e) : "r"(y), "f"(s));
  asm("fma.rn.f16x2 %0, %0, %1, %2;" : "+r"(y) : "r"(cm), "r"(y & 0xFC00FC00u));
}

__device__ __forceinline__ float mish(float z) {
  const float e = ex2(z);
  const float r = rcp(fmaf(e, e + 2.f, 2.f));
  return z * fmaf(r, -2.f * LN2, LN2);
}

__device__ __forceinline__ void mish_block(float* c, float rs0, float rs1, const float* bias, uint32_t* r) {
  pin<8>(c);
  const float2 b = *(const float2*)bias, d = *(const float2*)(bias + 8);
  r[0] = pack_bf16(mish(fmaf(c[0], rs0, b.x)), mish(fmaf(c[1], rs0, b.y)));
  r[4] = pack_bf16(mish(fmaf(c[2], rs1, b.x)), mish(fmaf(c[3], rs1, b.y)));
  r[1] = pack_bf16(mish(fmaf(c[4], rs0, d.x)), mish(fmaf(c[5], rs0, d.y)));
  r[5] = pack_bf16(mish(fmaf(c[6], rs1, d.x)), mish(fmaf(c[7], rs1, d.y)));
  pin<2>(r); pin<2>(r + 4);
}

__device__ __forceinline__ void attention_slow(const uint32_t* qa, int lane, float* o  ) {
  const int g = lane >> 2, t = lane & 3;
  float m0 = -INFINITY, m1 = -INFINITY, l0 = 0.f, l1 = 0.f;
  float acc[8] = {0.f, 0.f, 0.f, 0.f, 0.f, 0.f, 0.f, 0.f};
  const float sc = 0.25f * LOG2E * 0x1p70f;
#pragma unroll 1
  for (int k0 = 0; k0 < S_; k0 += 16) {
    float s[2][4];
#pragma unroll
    for (int h = 0; h < 2; h++) {
      const __nv_bfloat16* kp = g_KV + (size_t)(k0 + 8 * h + g) * 16 + 2 * t;
      s[h][0] = s[h][1] = s[h][2] = s[h][3] = 0.f;
      mma_bf16(s[h], qa, __ldcg((const uint32_t*)kp), __ldcg((const uint32_t*)(kp + 8)));
    }
    float x0 = fmaxf(fmaxf(s[0][0], s[0][1]), fmaxf(s[1][0], s[1][1])), x1 = fmaxf(fmaxf(s[0][2], s[0][3]), fmaxf(s[1][2], s[1][3]));
    x0 = fmaxf(x0, __shfl_xor_sync(~0u, x0, 1)); x0 = fmaxf(x0, __shfl_xor_sync(~0u, x0, 2));
    x1 = fmaxf(x1, __shfl_xor_sync(~0u, x1, 1)); x1 = fmaxf(x1, __shfl_xor_sync(~0u, x1, 2));
    const float n0 = fmaxf(m0, x0), n1 = fmaxf(m1, x1);
    const float a0 = ex2((m0 - n0) * sc), a1 = ex2((m1 - n1) * sc);
    m0 = n0; m1 = n1;
    uint32_t pa[4];
    float p[2][4];
#pragma unroll
    for (int h = 0; h < 2; h++) {
      p[h][0] = ex2((s[h][0] - n0) * sc); p[h][1] = ex2((s[h][1] - n0) * sc);
      p[h][2] = ex2((s[h][2] - n1) * sc); p[h][3] = ex2((s[h][3] - n1) * sc);
      pa[2 * h] = pack_bf16(p[h][0], p[h][1]); pa[2 * h + 1] = pack_bf16(p[h][2], p[h][3]);
    }
    l0 = l0 * a0 + (p[0][0] + p[0][1] + p[1][0] + p[1][1]);
    l1 = l1 * a1 + (p[0][2] + p[0][3] + p[1][2] + p[1][3]);
    acc[0] *= a0; acc[1] *= a0; acc[4] *= a0; acc[5] *= a0;
    acc[2] *= a1; acc[3] *= a1; acc[6] *= a1; acc[7] *= a1;
#pragma unroll
    for (int dh = 0; dh < 2; dh++) {
      uint32_t vb[2];
#pragma unroll
      for (int kh = 0; kh < 2; kh++) {
        uint32_t w[2];
#pragma unroll
        for (int e = 0; e < 2; e++) {
          w[e] = __ldcg((const unsigned short*)g_KV + (S_ + k0 + 8 * kh + 2 * t + e) * 16 + dh * 8 + g);
        }
        vb[kh] = w[0] | (w[1] << 16);
      }
      mma_bf16(acc + 4 * dh, pa, vb[0], vb[1]);
    }
  }
  l0 += __shfl_xor_sync(~0u, l0, 1); l0 += __shfl_xor_sync(~0u, l0, 2);
  l1 += __shfl_xor_sync(~0u, l1, 1); l1 += __shfl_xor_sync(~0u, l1, 2);
  const float i0 = 1.f / l0, i1 = 1.f / l1;
  o[0] = acc[0] * i0; o[1] = acc[1] * i0; o[2] = acc[2] * i1; o[3] = acc[3] * i1;
  o[4] = acc[4] * i0; o[5] = acc[5] * i0; o[6] = acc[6] * i1; o[7] = acc[7] * i1;
}

__global__ void __launch_bounds__(384, 1) fused_block_kernel(const __grid_constant__ Params p) {
  extern __shared__ __align__(1024) uint8_t smem[];
  const uint32_t sb = (uint32_t)__cvta_generic_to_shared(smem);
  const uint32_t bar0 = sb + OFF_MISC;
  auto BAR = [&](int i) { return bar0 + 8 * i; };
  const int tid = threadIdx.x, lane = tid & 31;
  const int warp = __shfl_sync(~0u, tid >> 5, 0);
  const int wg = warp >> 2;
  const int bid = blockIdx.x;
  const int ti = bid >> 3, j = bid & 7;
  const int kh_ = j >> 2, nt = j & 3;

  MARK(0);
  const int lead = j >> 1;
  if (tid == 256) {
#pragma unroll
    for (int i = 0; i < 8; i++) mbar_init(BAR(B_X + i), 1);
    mbar_init(BAR(B_W), 1); mbar_init(BAR(B_W + 1), 1);
    asm volatile("fence.proxy.async.shared::cta;" ::: "memory");
#pragma unroll
    for (int w = 0; w < 8; w++) {
      const int v = (0x36147250 >> (4 * w)) & 7;
      mbar_expect(BAR(B_X + v), 16384);
      tma3(sb + v * 16384, &p.x3, 0, ti * 128 + v * 16, 0, BAR(B_X + v));
    }
    mbar_expect(BAR(B_W), U_);
    tma2(sb + 4 * U_, &p.w1s, j * 224 + 192, 0, BAR(B_W)); tma2(sb + 4 * U_ + 16384, &p.w1s, j * 224 + 192, 256, BAR(B_W));
    mbar_expect(BAR(B_W + 1), U_);
    tma2(sb + 5 * U_, &p.w1, j * 224, 0, BAR(B_W + 1));
  }
  if (tid == 288) {
#pragma unroll
    for (int i = 0; i < 49; i++)
      if (i != B_W && i != B_W + 1 && i != 6 && i != 7 && (i < 29 || i > 32) && i != 45 && i != 46) mbar_init(BAR(i), ((MASK8 >> i) & 1) ? 8 : ((MASK4 >> i) & 1) ? 4 : 1);
    asm volatile("fence.proxy.async.shared::cta;" ::: "memory");
  }
  if (warp == 10 && j < 4) {
    const uint4* src = (const uint4*)((j & 1) ? p.wv : p.wk) + lane;
    const uint32_t dst = sb + OFF_WKV + ((lane ^ ((lane >> 3) & 1)) << 4);
#pragma unroll 4
    for (int i = 0; i < 32; i++) asm volatile("cp.async.cg.shared.global [%0], [%1], 16;" ::"r"(dst + i * 512), "l"(src + i * 32) : "memory");
  }
  MARK(17);
  __syncthreads();
  MARK(18);

  if (wg == 2) {
    asm volatile("setmaxnreg.dec.sync.aligned.u32 24;");
    auto unit = [&](int u, int slot, const CUtensorMap* m, int col, int row) { mbar_expect(BAR(B_W + u), U_); tma2(sb + slot * U_, m, col, row, BAR(B_W + u)); };
    if (warp == 8) {
      if (lane == 0) {
        if (sb & 1023) __trap();
        mbar_wait(BAR(B_XE + 1), 0);
        unit(2, 2, &p.w1, j * 224, 256); unit(3, 3, &p.w1, j * 224 + 64, 0);
        mbar_wait(BAR(B_XE), 0);
        unit(4, 0, &p.w1, j * 224 + 64, 256); unit(5, 1, &p.w1, j * 224 + 128, 0);
        l2_prefetch((const uint8_t*)p.pwq + bid * 4096, 4096);
        mbar_wait(BAR(B_WE), 0);
        unit(6, 4, &p.w1, j * 224 + 128, 256);
        l2_prefetch((const uint8_t*)p.pw2 + bid * 14336, 14336);
        l2_prefetch((const uint8_t*)p.pwo + bid * 4096, 4096);
        mbar_wait(BAR(B_WE + 1), 0);
        unit(7, 2, &p.wq, j * 64, 0);
        mbar_wait(BAR(B_WE + 2), 0);
        unit(8, 3, &p.wq, j * 64, 256);
        mbar_sleep(BAR(B_O1D), 0);
        mbar_expect(BAR(B_XR), 16384);
        tma2(sb + OFF_XRES, &p.x2, nt * 128 + kh_ * 64, ti * 128, BAR(B_XR));
      }
    } else if (warp == 9) {
      if (j < 4 && !(j & 1)) {
        mbar_wait(BAR(B_KVD), 0);
        MARKH(19);
        const int ch = lane >> 4, dd = lane & 15, col = (ti * 2 + lead) * 2 + ch;
        const float* kv = (const float*)(smem + OFF_STG) + ch * 32 * 20;
        uint8_t* dst = g_kv + (dd >> 3) * 4096 + col * 16 + (dd & 7) * 2;
        const float scale = is_mufu((col >> 3) * 2) ? 0x1p70f : 0x1p-69f;
        float rec = 0.f;
#pragma unroll 8
        for (int tau = 0; tau < 32; tau++) {
          const float h = __uint_as_float(pack_bf16(0.f, kv[tau * 20 + dd] * (kv[tau * 20 + 16] * (0.25f * LOG2E)) - rec));
          rec += h;
          *(unsigned short*)(dst + (tau >> 2) * KV_STAGE + (tau & 3) * 1024) = pack_bf16(h * scale, 0.f);
        }
        __syncwarp();
        MARKH(21);
        if (lane == 0) signal_counter(&g_cnt[CNT_KV * 32]);
        MARKH(22);
      }
      __syncwarp();
      mbar_wait(BAR(B_WE + 1), 0);
      auto kv_load = [&](int it) {
        mbar_expect(BAR(B_KF + (it & 1)), KV_STAGE);
        bulk_load(sb + OFF_KV + (it & 1) * KV_STAGE, g_kv + (it & 7) * KV_STAGE, KV_STAGE, BAR(B_KF + (it & 1)));
      };
      if (lane == 0) { wait_counter<40>(&g_cnt[CNT_KV * 32], 96); fence_async_all(); kv_load(0); kv_load(1); }
      __syncwarp();
      MARKH(24);
      const float k2 = __uint_as_float(__reduce_max_sync(~0u, __ldcg(g_kmax + lane))), v2 = __uint_as_float(__reduce_max_sync(~0u, __ldcg(g_kmax + 32 + lane)));
      if (lane == 0) {
        *(volatile uint32_t*)(smem + OFF_KMAX) = (k2 <= 1e30f && v2 >= 0.01f) ? 0 : 3;
        mbar_arrive(BAR(B_KM));
        for (int it = 2; it < 8; it++) { mbar_wait(BAR(B_KE + (it & 1)), ((it >> 1) - 1) & 1); kv_load(it); }
      }
    } else if (warp == 10) {
      asm volatile("cp.async.wait_all;" ::: "memory");
      fence_async_smem();
      __syncwarp();
      if (lane == 0) mbar_arrive(BAR(B_WKV));
      for (int i = lane; i < 224; i += 32) ((float*)(smem + OFF_BIAS))[i] = __bfloat162float(p.b1[j * 224 + i]) * LOG2E;
      __syncwarp();
      if (lane == 0) mbar_arrive(BAR(B_BI));
      if (j < 4) {
        mbar_wait(BAR(B_KVD), 0);
        const int tile = ti * 2 + lead;
        uint32_t mx = 0;
#pragma unroll 1
        for (int h = 0; h < 2; h++) {
          const int tau = h * 16 + (lane >> 1), row = (lane & 1) * 32 + tau;
          const float* kv = (const float*)(smem + OFF_STG) + row * 20;
          const float rs = kv[16];
          const int col = tile * 2 + (lane & 1);
          const uint32_t w2 = pack_f16(0.f, is_mufu((col >> 3) * 2) ? 0.5f : 0.5f * ex2(DRIFT * (tau + 1)));
          const float w = __half2float(__ushort_as_half(w2 >> 16));
          uint8_t* img = g_kv + (tau >> 2) * KV_STAGE + 8192 + ((tau & 3) * 64 + col) * 16;
          float n = 0.f;
#pragma unroll
          for (int dh = 0; dh < 2; dh++) {
            float4 u = *(const float4*)(kv + dh * 8), v = *(const float4*)(kv + dh * 8 + 4);
            u.x *= rs; u.y *= rs; u.z *= rs; u.w *= rs; v.x *= rs; v.y *= rs; v.z *= rs; v.w *= rs;
            n += u.x * u.x + u.y * u.y + u.z * u.z + u.w * u.w + v.x * v.x + v.y * v.y + v.z * v.z + v.w * v.w;
            *(uint4*)(g_KV + ((j & 1) * S_ + tile * 64 + row) * 16 + dh * 8) =
                make_uint4(pack_bf16(u.x, u.y), pack_bf16(u.z, u.w), pack_bf16(v.x, v.y), pack_bf16(v.z, v.w));
            if (j & 1) *(uint4*)(img + dh * 4096) = make_uint4(pack_f16(u.x * w, u.y * w), pack_f16(u.z * w, u.w * w), pack_f16(v.x * w, v.y * w), pack_f16(v.z * w, v.w * w));
          }
          if (j & 1) { const uint32_t ww = w2 | (w2 >> 16); *(uint4*)(img + 8192) = make_uint4(ww, ww, ww, ww); }
          mx = max(mx, __float_as_uint(n));
        }
        mx = __reduce_max_sync(~0u, mx);
        __syncwarp();
        if (lane == 0) {
          g_kmax[(j & 1) * 32 + tile] = mx;
          signal_counter(&g_cnt[CNT_KV * 32]);
        }
      }
      if (lane == 0) {
        mbar_sleep(BAR(B_WE + 3), 0); mbar_sleep(BAR(B_WE + 4), 0);
        wait_counter<100>(&g_cnt[(CNT_A + ti * 2 + kh_) * 32], 4);
        fence_async_all();
        int s = 0, ph = 1;
        for (int it = 0; it < 17; it++) {
          if (it == 5) mbar_sleep(BAR(B_O1D), 0);
          if (it >= G_SLOTS) mbar_wait(BAR(B_GE + s), ph);
          if (it == 14) { wait_counter<20>(&g_cnt[(CNT_O1 + ti) * 32], 8); fence_async_all(); mbar_arrive(BAR(B_O1R)); }
          mbar_expect(BAR(B_GF + s), 32768);
          const uint32_t dst = sb + s * G_STAGE, bar = BAR(B_GF + s);
          const int keep = nt * 2 + kh_;
          if (it == 16) {
            tma5(dst, &p.wo1, 1, 0, keep, bar);
          } else if (it >= 14) {
            const int st = kh_ * 2 + (it & 1);
            bulk_load(dst, g_H + (ti * 32 + 28 + st) * 16384, 16384, bar);
            tma5p(dst + 16384, &p.wo, keep * 64, st * 4, bar); tma5p(dst + 20480, &p.wo, keep * 64, st * 4 + 2, bar);
            tma5p(dst + 24576, &p.wo, (keep ^ 1) * 64, st * 4, bar); tma5p(dst + 28672, &p.wo, (keep ^ 1) * 64, st * 4 + 2, bar);
          } else {
            const int st = kh_ * 14 + it;
            bulk_load(dst, g_H + (ti * 32 + st) * 16384, 16384, bar);
            tma5p(dst + 16384, &p.w2, keep * 64, st * 2, bar); tma5p(dst + 24576, &p.w2, (keep ^ 1) * 64, st * 2, bar);
          }
          if (++s == G_SLOTS) { s = 0; ph ^= 1; }
        }
        if (atomicAdd(&g_cnt[CNT_DONE * 32], 1u) == 127u) {
          for (int i = 0; i < CNT_N; i++) g_cnt[i * 32] = 0;
        }
      }
    } else {
      if (lane == 0) {
        mbar_sleep(BAR(B_AD), 0);
        signal_counter(&g_cnt[(CNT_A + ti * 2 + kh_) * 32]);
      }
      __syncwarp();
#pragma unroll 4
      for (int i = 0; i < 32; i++) __stcg(&g_X[(bid ^ 4) * 1024 + i * 32 + lane], make_uint4(0, 0, 0, 0));
      __syncwarp();
      if (lane == 0) {
        mbar_sleep(BAR(B_O1D), 0);
        signal_counter(&g_cnt[(CNT_O1 + ti) * 32]);
      }
    }
  } else {
    const int g = lane >> 2, t = lane & 3;
    auto lane_off = [&]() {
      uint32_t l;
      asm volatile("mov.u32 %0, %%laneid;" : "=r"(l));
      return (l & 15) * 128 + (((l >> 4) ^ (l & 7)) << 4);
    };
    auto store_pair = [&](int n, const uint32_t* r) {
      uint32_t l;
      asm volatile("mov.u32 %0, %%laneid;" : "=r"(l));
      uint8_t* dst = g_H + ((ti * 32 + (n >> 1)) * 16384 + warp * 2048 + (l >> 2) * 128 + ((((n & 1) * 4 + (l & 3)) ^ (l >> 2)) << 4));
      asm volatile("st.global.cg.v4.u32 [%0], {%1,%2,%3,%4};\nst.global.cg.v4.u32 [%0+1024], {%5,%6,%7,%8};" ::"l"(dst), "r"(r[0]), "r"(r[1]), "r"(r[2]), "r"(r[3]),
                   "r"(r[4]), "r"(r[5]), "r"(r[6]), "r"(r[7]) : "memory");
    };

    asm volatile("setmaxnreg.inc.sync.aligned.u32 240;");
    const int row0 = ti * 128 + warp * 16;
    uint32_t qf[4][4];
    {
      uint32_t a[32][4];
      uint32_t lo64 = lane_off();
      mbar_wait(BAR(B_X + warp), 0);
      MARK(1);
#pragma unroll
      for (int kb = 0; kb < 32; kb++) ldsm4(a[kb], sb + warp * 16384 + (kb >> 2) * 2048 + (lo64 ^ ((kb & 3) << 5)));
      float cs[4][4];
#pragma unroll
      for (int c = 0; c < 4; c++) cs[c][0] = cs[c][1] = cs[c][2] = cs[c][3] = 0.f;
#pragma unroll
      for (int kb = 0; kb < 32; kb++) mma_bf16(cs[kb & 3], a[kb], 0x3F803F80u, 0x3F803F80u);
      const float mean0 = ((cs[0][0] + cs[1][0]) + (cs[2][0] + cs[3][0])) * (1.f / D_);
      const float mean1 = ((cs[0][2] + cs[1][2]) + (cs[2][2] + cs[3][2])) * (1.f / D_);
      __syncwarp();
      if (lane == 0) mbar_arrive(BAR(B_XE + wg));
      const uint32_t m0 = pack_bf16(mean0, mean0), m1 = pack_bf16(mean1, mean1);
#pragma unroll
      for (int kb = 0; kb < 32; kb++)
#pragma unroll
        for (int r = 0; r < 4; r++) asm("sub.rn.bf16x2 %0, %0, %1;" : "+r"(a[kb][r]) : "r"((r & 1) ? m1 : m0));
#pragma unroll
      for (int c = 0; c < 2; c++) cs[c][0] = cs[c][1] = cs[c][2] = cs[c][3] = 0.f;
#pragma unroll
      for (int kb = 0; kb < 32; kb += 4) {
        uint32_t u[4];
#pragma unroll
        for (int r = 0; r < 4; r++) {
          asm("mul.rn.bf16x2 %0, %1, %1;" : "=r"(u[r]) : "r"(a[kb][r]));
#pragma unroll
          for (int e = 1; e < 4; e++) asm("fma.rn.bf16x2 %0, %1, %1, %0;" : "+r"(u[r]) : "r"(a[kb + e][r]));
        }
        mma_bf16(cs[(kb >> 2) & 1], u, 0x3F803F80u, 0x3F803F80u);
      }
      const float dm0 = mean0 - __uint_as_float(m0 << 16), dm1 = mean1 - __uint_as_float(m1 << 16);
      const float rs0 = rsqrtf(fmaxf((cs[0][0] + cs[1][0]) * (1.f / D_) - dm0 * dm0, 0.f) + 1e-5f);
      const float rs1 = rsqrtf(fmaxf((cs[0][2] + cs[1][2]) * (1.f / D_) - dm1 * dm1, 0.f) + 1e-5f);
      MARK(2);
      {
        if (j < 4 && wg == lead) {
          float kv[8];
          mbar_wait(BAR(B_WKV), 0);
          const uint64_t d = mkdesc(sb + OFF_WKV, 16, 256, 3);
          pin<128>(&a[0][0]);
          wg_fence();
#pragma unroll
          for (int kb = 0; kb < 32; kb++) wg_rs16t(kv, a[kb], d + kb * 32, kb > 0);
          wg_commit();
          wg_wait<0>();
          pin<8>(kv);
          float* ks = (float*)(smem + OFF_STG) + ((warp & 3) * 16 + g) * 20 + 2 * t;
          *(float2*)ks = make_float2(kv[0], kv[1]); *(float2*)(ks + 8) = make_float2(kv[4], kv[5]);
          *(float2*)(ks + 160) = make_float2(kv[2], kv[3]); *(float2*)(ks + 168) = make_float2(kv[6], kv[7]);
          if (t == 0) { ks[16] = rs0; ks[176] = rs1; }
          __syncwarp();
          if (lane == 0) mbar_arrive(BAR(B_KVD));
        }
      }
      MARK(16);
      float acc0[32], acc1[32];
      const float* bias = (const float*)(smem + OFF_BIAS) + t * 2;
      {
        mbar_wait(BAR(B_W), 0);
        const uint64_t d = mkdesc(sb + 4 * U_, 16, 512, 2);
        pin<128>(&a[0][0]);
        wg_fence();
#pragma unroll
        for (int kb = 0; kb < 32; kb++) wg_rs32t(acc1, a[kb], d + kb * 64, kb > 0);
        wg_commit();
        wg_wait<0>();
        pin<16>(acc1);
        if (lane == 0) mbar_arrive(BAR(B_WE));
        mbar_wait(BAR(B_BI), 0);
      }
      MARK(3);
      const float rl0 = rs0 * LOG2E, rl1 = rs1 * LOG2E;
      auto tile = [&](int n, float* acc, float* prev, uint32_t base0, uint32_t base1) {
        pin<1>(&base0); pin<1>(&base1);
        uint32_t r[8];
        mbar_wait(BAR(B_W + 2 * n - 1), 0);
        const uint64_t d0 = mkdesc(base0, 16, 1024, 1), d1 = mkdesc(base1, 16, 1024, 1);
        pin<128>(&a[0][0]);
        wg_fence();
#pragma unroll
        for (int kb = 0; kb < 32; kb++) {
          if (kb == 16) { mbar_wait(BAR(B_W + 2 * n), 0); wg_fence(); }
          wg_rs64t(acc, a[kb], (kb < 16 ? d0 : d1) + (kb & 15) * 128, kb > 0);
          if (kb == 31) wg_commit();
          if ((kb & 7) == 7) {
            const int q = kb >> 3;
            if (n == 1) {
              if (q & 1) mish_block(prev + 4 * (q - 1), rl0, rl1, bias + 192 + 8 * (q - 1), r + (q - 1));
              if (q == 3) store_pair(j * 7 + 6, r);
            } else {
              mish_block(prev + 8 * q, rl0, rl1, bias + (n - 2) * 64 + 16 * q, r + 2 * (q & 1));
              if (q & 1) store_pair(j * 7 + (n - 2) * 2 + (q >> 1), r);
            }
          }
        }
        if (n == 4) { __syncwarp(); if (lane == 0) mbar_arrive(BAR(B_AD)); }
        wg_wait<0>();
        pin<32>(acc);
        if (lane == 0) mbar_arrive(BAR(B_WE + n));
      };
      tile(1, acc0, acc1, sb + 5 * U_, sb + 2 * U_);
      MARK(23);
      tile(2, acc1, acc0, sb + 3 * U_, sb);
      MARK(4);
      tile(3, acc0, acc1, sb + U_, sb + 4 * U_);
      MARK(25);
      tile(4, acc1, acc0, sb + 2 * U_, sb + 3 * U_);
      MARK(5);
#pragma unroll
      for (int h = 0; h < 4; h++)
#pragma unroll
        for (int r = 0; r < 4; r++) {
          const float qs = (LN2 * 0x1p-70f) * ((r & 1) ? rl1 : rl0);
          qf[h][r] = pack_bf16(acc1[8 * h + 2 * r] * qs, acc1[8 * h + 2 * r + 1] * qs);
        }
    }

    MARK(7);
    float acc[64];
    int gs = 0, gph = 0;
    {
      mbar_wait(BAR(B_KM), 0);
      uint32_t bad = *(volatile uint32_t*)(smem + OFF_KMAX);
      uint32_t cm = 0x38003800u;
      pin<1>(&cm);
      auto store_o = [&](int ps, const uint32_t* r) {
        if (ps) {
          uint4* dst = &g_O1[((ti * 8 + warp) * 16 + j * 2) * 32 + lane];
          dst[0] = make_uint4(r[0], r[1], r[2], r[3]); dst[32] = make_uint4(r[4], r[5], r[6], r[7]);
        } else {
          const uint32_t ro[8] = {r[0], r[2], r[4], r[6], r[1], r[3], r[5], r[7]};
          store_pair(56 + j, ro);
        }
      };
      const uint64_t dk0 = mkdesc(sb + OFF_KV, 4096, 128, 0), dv0 = mkdesc(sb + OFF_KV + 8192, 128, 4096, 0);
      uint32_t P[3][8], o[4][6], tmp[4] = {0, 0, 0, 0}, lt[4] = {0, 0, 0, 0};
      float s[4][32];
#pragma unroll
      for (int r = 0; r < 8; r++) P[0][r] = P[1][r] = P[2][r] = 0;
#pragma unroll
      for (int c = 0; c < 4; c++) {
#pragma unroll
        for (int r = 0; r < 32; r++) s[c][r] = is_mufu(r >> 1) ? -P_SHIFT : __uint_as_float(POLY_INIT);
#pragma unroll
        for (int r = 0; r < 6; r++) o[c][r] = 0;
        pin<32>(s[c]); pin<6>(o[c]); pin<4>(qf[c]);
      }
      mbar_wait(BAR(B_KF), 0);
      wg_fence();
#pragma unroll
      for (int c = 0; c < 4; c++) wg_qk64(s[c], qf[c], dk0, 1);
      wg_commit();
      wg_wait<0>();
      {
#pragma unroll 1
        for (int body = 0; body < 8; body++) {
          const uint32_t cur = (body & 1) * (KV_STAGE >> 4), nxt = (KV_STAGE >> 4) - cur;
#pragma unroll
          for (int u = 0; u < 4; u++) {
            if (u == 3 && body < 7) mbar_wait(BAR(B_KF + ((body + 1) & 1)), ((body + 1) >> 1) & 1);
            const uint64_t dkn = dk0 + (u == 3 ? nxt : cur + (u + 1) * 64), dvc = dv0 + cur + u * 64;
#pragma unroll
            for (int c = 0; c < 4; c++) {
              if (u * 4 + c >= 1) wg_wait<1>();
              pin<32>(s[c]);
              uint32_t *y = P[(2 * (u * 4 + c)) % 3], *z = P[(2 * (u * 4 + c) + 1) % 3];
              const float* sc = s[c];
#pragma unroll
              for (int r = 0; r < 8; r++)
                if (!is_mufu(r)) { y[r] = exp_pack(sc[2 * r], sc[2 * r + 1]); z[r] = exp_pack(sc[16 + 2 * r], sc[17 + 2 * r]); }
              y[4] = __float_as_uint(ex2(sc[8])); tmp[0] = __float_as_uint(ex2(sc[9])); y[5] = __float_as_uint(ex2(sc[10]));
              exp_poly(y[0], cm, tmp[1], sc[11]); exp_poly(y[1], cm, z[4], sc[24]); exp_poly(y[2], cm);
              exp_poly(y[3], cm, tmp[2], sc[25]); exp_poly(y[6], cm); exp_poly(y[7], cm, z[5], sc[26]);
              y[4] = pack_f16(__uint_as_float(y[4]), __uint_as_float(tmp[0])); y[5] = pack_f16(__uint_as_float(y[5]), __uint_as_float(tmp[1]));
              pin<8>(y);
              wg_fence();
              wg_pv24(o[c], y, dvc, 1); wg_pv24(o[c], y + 4, dvc + 16, 1);
              wg_commit();
              exp_poly(z[0], cm); exp_poly(z[1], cm, tmp[3], sc[27]); exp_poly(z[2], cm);
              exp_poly(z[3], cm); exp_poly(z[6], cm); exp_poly(z[7], cm);
              z[4] = pack_f16(__uint_as_float(z[4]), __uint_as_float(tmp[2])); z[5] = pack_f16(__uint_as_float(z[5]), __uint_as_float(tmp[3]));
              pin<8>(z); pin<32>(s[c]);
              wg_fence();
              wg_qk64(s[c], qf[c], dkn, 1);
              wg_pv24(o[c], z, dvc + 32, 1); wg_pv24(o[c], z + 4, dvc + 48, 1);
              wg_commit();
            }
          }
          wg_wait<0>();
          if (lane == 0) mbar_arrive(BAR(B_KE + (body & 1)));
#pragma unroll
          for (int c = 0; c < 4; c++) {
            pin<2>(&o[c][4]);
            asm("add.rn.f16x2 %0, %0, %1;" : "+r"(lt[c]) : "r"(__byte_perm(o[c][4], o[c][5], 0x5410)));
            pin<1>(&lt[c]);
            o[c][4] = o[c][5] = 0;
            pin<2>(&o[c][4]);
          }
        }
#pragma unroll
        for (int c = 0; c < 4; c++) { pin<6>(o[c]); pin<32>(s[c]); }
#pragma unroll
        for (int ps = 0; ps < 2; ps++) {
          uint32_t r[8];
          bool ok = true;
#pragma unroll
          for (int c = 0; c < 2; c++) {
            const uint32_t* oc = o[2 * ps + c];
            const float2 l = __half22float2(*(const __half2*)&lt[2 * ps + c]);
            ok = ok && l.x >= 8.f && l.y >= 8.f && l.x <= 65504.f && l.y <= 65504.f;
            const float i0 = rcp(l.x), i1 = rcp(l.y);
#pragma unroll
            for (int e = 0; e < 4; e++) {
              ok = ok && ((oc[e] & 0x7C00u) != 0x7C00u) && ((oc[e] & 0x7C000000u) != 0x7C000000u);
              const float2 f = __half22float2(*(const __half2*)&oc[e]);
              r[4 * c + e] = pack_bf16(f.x * ((e & 1) ? i1 : i0), f.y * ((e & 1) ? i1 : i0));
            }
          }
          if (!__all_sync(~0u, ok)) bad |= 1u << ps;
          store_o(ps, r);
        }
        MARK(9);
      }
      if (bad) {
#pragma unroll 1
        for (int ps = 0; ps < 2; ps++) {
          if ((bad >> ps) & 1) {
            uint32_t r[8];
#pragma unroll 1
            for (int c = 0; c < 2; c++) {
              uint32_t qa[4];
#pragma unroll
              for (int e = 0; e < 4; e++) qa[e] = ps ? (c ? qf[3][e] : qf[2][e]) : (c ? qf[1][e] : qf[0][e]);
              float o[8];
              attention_slow(qa, lane, o);
#pragma unroll
              for (int e = 0; e < 4; e++) { r[e] = r[4 + e]; r[4 + e] = pack_bf16(o[(e & 1) * 2 + (e >> 1) * 4], o[(e & 1) * 2 + (e >> 1) * 4 + 1]); }
            }
            store_o(ps, r);
          }
        }
      }
      __syncwarp();
      if (lane == 0) mbar_arrive(BAR(B_O1D));
    }

    const uint64_t da0 = mkdesc(sb + wg * 8192, 16, 1024, 1), db0 = mkdesc(sb + 16384, 8192, 1024, 1);
    auto stage = [&](int it) {
      mbar_wait(BAR(B_GF + gs), gph);
      const uint64_t da = da0 + gs * (G_STAGE >> 4), db = db0 + gs * (G_STAGE >> 4);
      pin<64>(acc);
      wg_fence();
#pragma unroll
      for (int k = 0; k < 4; k++) wg_ss128t(acc, da + k * 2, db + k * 128, it > 0 || k > 0);
      wg_commit();
      wg_wait<1>();
      if (it > 0 && lane == 0) mbar_arrive(BAR(B_GE + (gs == 0 ? G_SLOTS - 1 : gs - 1)));
      if (++gs == G_SLOTS) { gs = 0; gph ^= 1; }
    };
    MARK(10);
#pragma unroll 1
    for (int it = 0; it < 13; it++) stage(it);
    mbar_wait(BAR(B_O1R), 0);
    uint32_t a[16][4];
#pragma unroll
    for (int kb = 0; kb < 16; kb++)
      asm volatile("ld.global.cg.v4.u32 {%0,%1,%2,%3}, [%4];" : "=r"(a[kb][0]), "=r"(a[kb][1]), "=r"(a[kb][2]), "=r"(a[kb][3])
                   : "l"(&g_O1[((ti * 8 + warp) * 16 + kb) * 32 + lane]) : "memory");
#pragma unroll 1
    for (int it = 13; it < 16; it++) stage(it);
    wg_wait<0>();
    pin<64>(acc);
    MARK(11);
#pragma unroll
    for (int b = 0; b < 4; b++) {
      const float* c = acc + 32 + 8 * b;
      auto enc = [](float lo, float hi) { return max(pack_bf16(lo, hi) ^ 0x80008000u, 1u); };
      __stcg(&g_X[(bid * 4 + b) * 256 + tid], make_uint4(enc(c[0], c[1]), enc(c[2], c[3]), enc(c[4], c[5]), enc(c[6], c[7])));
    }
    {
      mbar_wait(BAR(B_GF + 16 % G_SLOTS), (16 / G_SLOTS) & 1);
      const uint64_t d = mkdesc(sb + (16 % G_SLOTS) * G_STAGE, 16, 1024, 1);
      pin<64>(&a[0][0]); pin<32>(acc);
      wg_fence();
#pragma unroll
      for (int kb = 0; kb < 16; kb++) wg_rs64t(acc, a[kb], d + kb * 128, 1);
      wg_commit();
    }
    const uint32_t lo64 = lane_off();
    mbar_wait(BAR(B_XR), 0);
    uint32_t xr[4][4];
#pragma unroll
    for (int b = 0; b < 4; b++) ldsm4(xr[b], sb + OFF_XRES + warp * 2048 + (lo64 ^ (b << 5)));
    uint32_t xv[4][4];
    {
      uint4* src = &g_X[((bid ^ 4) * 4) * 256 + tid];
      asm volatile(
          "{\n.reg .pred p;\n.reg .u32 n, m;\nmov.u32 n, 0;\n"
          "LAB_POLL:\n"
          "ld.relaxed.gpu.global.v4.u32 {%0,%1,%2,%3}, [%16];\n"
          "ld.relaxed.gpu.global.v4.u32 {%4,%5,%6,%7}, [%16+4096];\n"
          "ld.relaxed.gpu.global.v4.u32 {%8,%9,%10,%11}, [%16+8192];\n"
          "ld.relaxed.gpu.global.v4.u32 {%12,%13,%14,%15}, [%16+12288];\n"
          "min.u32 m, %0, %1;\nmin.u32 m, m, %2;\nmin.u32 m, m, %3;\nmin.u32 m, m, %4;\nmin.u32 m, m, %5;\nmin.u32 m, m, %6;\nmin.u32 m, m, %7;\n"
          "min.u32 m, m, %8;\nmin.u32 m, m, %9;\nmin.u32 m, m, %10;\nmin.u32 m, m, %11;\nmin.u32 m, m, %12;\nmin.u32 m, m, %13;\nmin.u32 m, m, %14;\nmin.u32 m, m, %15;\n"
          "setp.ne.u32 p, m, 0;\n"
          "@p bra LAB_DONE;\n"
          "nanosleep.u32 64;\n"
          "add.u32 n, n, 1;\nsetp.lt.u32 p, n, 4000000;\n"
          "@p bra LAB_POLL;\n"
          "trap;\n"
          "LAB_DONE:\n}\n"
          : "=r"(xv[0][0]), "=r"(xv[0][1]), "=r"(xv[0][2]), "=r"(xv[0][3]), "=r"(xv[1][0]), "=r"(xv[1][1]), "=r"(xv[1][2]), "=r"(xv[1][3]),
            "=r"(xv[2][0]), "=r"(xv[2][1]), "=r"(xv[2][2]), "=r"(xv[2][3]), "=r"(xv[3][0]), "=r"(xv[3][1]), "=r"(xv[3][2]), "=r"(xv[3][3])
          : "l"(src) : "memory");
      __syncwarp();
      MARK(12);
    }
    wg_wait<0>();
    pin<32>(acc);
    MARK(13);
#pragma unroll
    for (int b = 0; b < 4; b++) {
      uint32_t r[4];
#pragma unroll
      for (int h = 0; h < 4; h++) {
        const uint32_t v = xv[b][h] ^ 0x80008000u;
        r[h] = pack_bf16(acc[8 * b + 2 * h] + __uint_as_float(v << 16) + __uint_as_float(xr[b][h] << 16),
                         acc[8 * b + 2 * h + 1] + __uint_as_float(v & 0xFFFF0000u) + __uint_as_float(xr[b][h] & 0xFFFF0000u));
      }
      stsm4(sb + OFF_STG + warp * 2048 + (lo64 ^ (b << 5)), r[0], r[1], r[2], r[3]);
    }
    __syncwarp();
#pragma unroll
    for (int i = 0; i < 4; i++) {
      const int r = i * 4 + (lane >> 3);
      const uint4 v = *(const uint4*)(smem + OFF_STG + warp * 2048 + r * 128 + (((lane & 7) ^ (r & 7)) << 4));
      *(uint4*)(p.outp + (size_t)(row0 + r) * D_ + nt * 128 + kh_ * 64 + (lane & 7) * 8) = v;
    }
    MARK(14);
  }
}

typedef CUresult (*EncodeFn)(CUtensorMap*, CUtensorMapDataType, cuuint32_t, void*, const cuuint64_t*, const cuuint64_t*, const cuuint32_t*,
                             const cuuint32_t*, CUtensorMapInterleave, CUtensorMapSwizzle, CUtensorMapL2promotion, CUtensorMapFloatOOBfill);

void make_map(EncodeFn enc, CUtensorMap* m, const void* ptr, int rank, const cuuint64_t* dims, const cuuint64_t* strides, const cuuint32_t* box,
              CUtensorMapSwizzle sw) {
  const cuuint32_t es[5] = {1, 1, 1, 1, 1};
  enc(m, CU_TENSOR_MAP_DATA_TYPE_BFLOAT16, rank, const_cast<void*>(ptr), dims, strides, box, es, CU_TENSOR_MAP_INTERLEAVE_NONE, sw,
      CU_TENSOR_MAP_L2_PROMOTION_L2_128B, CU_TENSOR_MAP_FLOAT_OOB_FILL_NONE);
}
void map2(EncodeFn enc, CUtensorMap* m, const void* ptr, int cols, int rows, int bc, int br, CUtensorMapSwizzle sw) {
  const cuuint64_t dims[2] = {(cuuint64_t)cols, (cuuint64_t)rows}, st[1] = {(cuuint64_t)cols * 2};
  const cuuint32_t box[2] = {(cuuint32_t)bc, (cuuint32_t)br};
  make_map(enc, m, ptr, 2, dims, st, box, sw);
}
void map3(EncodeFn enc, CUtensorMap* m, const void* ptr, int cols, int rows, int br, int bb) {
  const cuuint64_t dims[3] = {64, (cuuint64_t)rows, (cuuint64_t)cols / 64}, st[2] = {(cuuint64_t)cols * 2, 128};
  const cuuint32_t box[3] = {64, (cuuint32_t)br, (cuuint32_t)bb};
  make_map(enc, m, ptr, 3, dims, st, box, CU_TENSOR_MAP_SWIZZLE_128B);
}

void mapp(EncodeFn enc, CUtensorMap* m, const void* ptr, int rows, int bp) {
  const cuuint64_t dims[5] = {512, 2, 4, 4, (cuuint64_t)rows / 32}, st[4] = {1024, 8 * 1024, 2 * 1024, 32 * 1024};
  const cuuint32_t box[5] = {64, 2, 4, 4, (cuuint32_t)bp};
  make_map(enc, m, ptr, 5, dims, st, box, CU_TENSOR_MAP_SWIZZLE_128B);
}

}

extern "C" void kernel_launch(void* const* d_in, const int* in_sizes, int n_in, void* d_out, int out_size) {
  (void)in_sizes; (void)n_in; (void)out_size;
  const void *x = d_in[0], *wq = d_in[1], *wk = d_in[2], *wv = d_in[3], *wo = d_in[4], *w1 = d_in[6], *b1 = d_in[7], *w2 = d_in[8];
  void* fn = nullptr;
  cudaDriverEntryPointQueryResult qr;
  cudaGetDriverEntryPoint("cuTensorMapEncodeTiled", &fn, cudaEnableDefault, &qr);
  EncodeFn enc = (EncodeFn)fn;
  Params p;
  map3(enc, &p.x3, x, D_, S_, 16, 8);
  map2(enc, &p.x2, x, D_, S_, 64, 128, CU_TENSOR_MAP_SWIZZLE_128B);
  map2(enc, &p.wq, wq, D_, D_, 64, 256, CU_TENSOR_MAP_SWIZZLE_128B);
  map2(enc, &p.w1, w1, F_, D_, 64, 256, CU_TENSOR_MAP_SWIZZLE_128B);
  map2(enc, &p.w1s, w1, F_, D_, 32, 256, CU_TENSOR_MAP_SWIZZLE_64B);
  mapp(enc, &p.w2, w2, F_, 2);
  mapp(enc, &p.wo, wo, D_, 1);
  {
    const cuuint64_t dims[5] = {64, 32, 2, 8, 8}, st[4] = {1024, 32 * 1024, 64 * 1024, 128};
    const cuuint32_t box1[5] = {64, 32, 1, 8, 1};
    make_map(enc, &p.wo1, wo, 5, dims, st, box1, CU_TENSOR_MAP_SWIZZLE_128B);
  }
  p.outp = (__nv_bfloat16*)d_out;
  p.wk = (const __nv_bfloat16*)wk; p.wv = (const __nv_bfloat16*)wv;
  p.b1 = (const __nv_bfloat16*)b1; p.pw2 = (const __nv_bfloat16*)w2; p.pwo = (const __nv_bfloat16*)wo; p.pwq = (const __nv_bfloat16*)wq;
  cudaFuncSetAttribute(fused_block_kernel, cudaFuncAttributeMaxDynamicSharedMemorySize, SMEM_BYTES);
  fused_block_kernel<<<128, 384, SMEM_BYTES>>>(p);
}
```
